```python
import torch

def _softmax(x, axis=-1):
    return torch.softmax(x, dim=axis)
def _gelu(x):
    return torch.nn.functional.gelu(x, approximate="tanh")
def _silu(x):
    return torch.nn.functional.silu(x)
def _sigmoid(x):
    return torch.sigmoid(x)
def _layernorm(x, axis=-1, eps=1e-5):
    m = x.mean(dim=axis, keepdim=True)
    v = x.var(dim=axis, keepdim=True, unbiased=False)
    return (x - m) / torch.sqrt(v + eps)
def _scatter_add(tgt, idx, src, axis=0):
    return tgt.clone().index_add_(axis, idx, src)
def _segment_sum(src, seg, n):
    out = torch.zeros((n,) + src.shape[1:], dtype=src.dtype)
    return out.index_add_(0, seg, src)
def _pad(x, pw):
    flat = tuple(v for pair in reversed(pw) for v in pair)
    return torch.nn.functional.pad(x, flat)

kernel_name = 'interleave_layers__linear_kernel_hedgehog__glu_gated_geglu__prompt'

def setup_inputs():

    _w = (lambda a: (lambda t: t.to(torch.bfloat16) if t.is_floating_point() else t)(torch.as_tensor(a)))
    def _A_setup():
        B, S, D, H = 1, 2048, 448, 16
        Dh = D // H
        return {
            "x": _w((lambda *s: torch.randn(*s, dtype=torch.bfloat16) * 0.05)(B, S, D)),
            "wqkv": _w((lambda *s: torch.randn(*s, dtype=torch.bfloat16) * 0.4)(D, 3 * D)),
            "w_phi": _w((lambda *s: torch.randn(*s, dtype=torch.bfloat16) * 0.4)(H, Dh, Dh) * (Dh ** -0.5)),
            "wo": _w((lambda *s: torch.randn(*s, dtype=torch.bfloat16) * 0.05)(D, D)),
        }
    _A_in = _A_setup()

    def _B_setup():
        B, S, Dm, Df = 1, 2048, 448, 1792
        return {
            "x": _w((lambda *s: torch.randn(*s, dtype=torch.bfloat16) * 0.05)(B, S, Dm)),
            "w_gate": _w((lambda *s: torch.randn(*s, dtype=torch.bfloat16) * 0.8)(Dm, Df) * (Dm ** -0.5)),
            "w_up": _w((lambda *s: torch.randn(*s, dtype=torch.bfloat16) * 0.8)(Dm, Df) * (Dm ** -0.5)),
            "w_down": _w((lambda *s: torch.randn(*s, dtype=torch.bfloat16) * 0.8)(Df, Dm) * (Df ** -0.5)),
        }
    _B_in = _B_setup()

    return {
        "A_x": _A_in["x"],
        "A_wqkv": _A_in["wqkv"],
        "A_w_phi": _A_in["w_phi"],
        "A_wo": _A_in["wo"],
        "B_x": _B_in["x"],
        "B_w_gate": _B_in["w_gate"],
        "B_w_up": _B_in["w_up"],
        "B_w_down": _B_in["w_down"],
    }

def reference(A_x, A_wqkv, A_w_phi, A_wo, B_x, B_w_gate, B_w_up, B_w_down):
    def _A_ref(x, wqkv, w_phi, wo):
        B, S, D = x.shape
        H = 16; Dh = D // H
        qkv = (lambda x, *d: x.permute(*d))((x @ wqkv).reshape(B, S, 3, H, Dh), 2, 0, 3, 1, 4)
        q, k, v = qkv[0], qkv[1], qkv[2]
        pq = torch.einsum("bhsd,hdf->bhsf", q, w_phi)
        pk = torch.einsum("bhsd,hdf->bhsf", k, w_phi)
        phi_q = torch.concatenate([_softmax(pq, axis=-1), _softmax(-pq, axis=-1)], axis=-1)
        phi_k = torch.concatenate([_softmax(pk, axis=-1), _softmax(-pk, axis=-1)], axis=-1)
        kv = torch.einsum("bhsf,bhsd->bhfd", phi_k, v)
        z  = torch.einsum("bhsf->bhf", phi_k)
        num = torch.einsum("bhqf,bhfd->bhqd", phi_q, kv)
        den = torch.einsum("bhqf,bhf->bhq", phi_q, z)[..., None] + 1e-6
        o = num / den
        return (lambda x, *d: x.permute(*d))(o, 0, 2, 1, 3).reshape(B, S, D) @ wo

    def _B_ref(x, w_gate, w_up, w_down):
        g = torch.einsum("bsd,df->bsf", x, w_gate)
        u = torch.einsum("bsd,df->bsf", x, w_up)
        h = _gelu(g) * u
        return torch.einsum("bsf,fd->bsd", h, w_down)

    x = A_x
    x = x + _A_ref(_layernorm(x, axis=-1), A_wqkv, A_w_phi, A_wo)
    x = x + _B_ref(_layernorm(x, axis=-1), B_w_gate, B_w_up, B_w_down)
    x = x + _A_ref(_layernorm(x, axis=-1), A_wqkv, A_w_phi, A_wo)
    x = x + _B_ref(_layernorm(x, axis=-1), B_w_gate, B_w_up, B_w_down)
    return x
```

```cpp
#include <cuda_runtime.h>
#include <cuda_bf16.h>
#include <cuda.h>
#include <stdint.h>


namespace {

constexpr int PD1 = 2000;
constexpr int PD2 = 300;
constexpr int PN0 = 2;
constexpr int SKEW = 1600;

constexpr int kS = 2048, kD = 448, kDF = 1792;
constexpr int NSLOT = 6, SLOT_BYTES = 16384;
constexpr int STAGES_PER_LAYER = 54, TOTAL_STAGES = 2 * STAGES_PER_LAYER;
constexpr uint32_t SM_A = 0;
constexpr uint32_t SM_RING = 114688;
constexpr uint32_t SM_WPHI = SM_RING + NSLOT * SLOT_BYTES;
constexpr uint32_t SM_KVB = SM_WPHI + 4096;
constexpr uint32_t SM_BAR = SM_KVB + 14336;
constexpr uint32_t BAR_FULL = SM_BAR, BAR_EMPTY = SM_BAR + 64, BAR_X = SM_BAR + 128, BAR_AUX = SM_BAR + 192, BAR_PUB = SM_BAR + 200, BAR_W = SM_BAR + 256, SM_PAR = SM_BAR + 208, BAR_GO = SM_BAR + 216;
constexpr uint32_t AFREE = NSLOT;
constexpr uint32_t SMEM_BYTES = SM_BAR + 320;

constexpr uint32_t AGBUF = 16 * 8 * 8 * 2048, PSRC = 8 * 1792, HSRC = 8 * 7168;

struct Maps { CUtensorMap x, kv, q, wo, g2, g3, u2, u3, dn; };

__device__ __align__(1024) uint4 g_ag[2][16 * 8 * 8 * 128];
__device__ uint32_t g_parity;
__device__ __align__(1024) uint4 g_part[16 * 8 * 3 * 8 * 112];
__device__ __align__(1024) uint4 g_h[16 * 8 * 8 * 448];
__device__ __align__(1024) uint4 g_kv1[8 * 16 * 16 * 32];
__device__ __align__(1024) uint4 g_kv2[8 * 512];

#define DEVI __device__ __forceinline__
DEVI uint32_t smem_u32(const void* p) { return (uint32_t)__cvta_generic_to_shared(p); }
DEVI void mbar_init(uint32_t bar, uint32_t cnt) { asm volatile("mbarrier.init.shared::cta.b64 [%0], %1;" ::"r"(bar), "r"(cnt) : "memory"); }
DEVI void mbar_expect_tx(uint32_t bar, uint32_t bytes) { asm volatile("mbarrier.arrive.expect_tx.shared::cta.b64 _, [%0], %1;" ::"r"(bar), "r"(bytes) : "memory"); }
DEVI void mbar_arrive(uint32_t bar) { asm volatile("mbarrier.arrive.shared::cta.b64 _, [%0];" ::"r"(bar) : "memory"); }
DEVI void mbar_wait(uint32_t bar, uint32_t parity) {
  asm volatile(
      "{\n.reg .pred p;\n.reg .u32 n;\nmov.u32 n, 0;\n"
      "W0: mbarrier.try_wait.parity.shared::cta.b64 p, [%0], %1;\n"
      "@p bra W1;\nadd.u32 n, n, 1;\nsetp.lt.u32 p, n, 4000000;\n@p bra W0;\ntrap;\nW1:\n}\n" ::"r"(bar), "r"(parity) : "memory");
}
DEVI void mbar_wait_c(uint32_t bar, uint32_t parity) {
  asm volatile("{\n.reg .pred p;\nW0: mbarrier.try_wait.parity.shared::cta.b64 p, [%0], %1;\n@!p bra W0;\n}\n" ::"r"(bar), "r"(parity) : "memory");
}
DEVI bool elect() { uint32_t p; asm volatile("{\n.reg .pred p;\nelect.sync _|p, 0xffffffff;\nselp.u32 %0, 1, 0, p;\n}\n" : "=r"(p)); return p; }
DEVI uint32_t mapa(uint32_t a, uint32_t r) { uint32_t o; asm("mapa.shared::cluster.u32 %0, %1, %2;" : "=r"(o) : "r"(a), "r"(r)); return o; }
DEVI void tma3(uint32_t dst, const CUtensorMap* m, int c0, int c1, uint32_t bar) {
  asm volatile("cp.async.bulk.tensor.3d.shared::cluster.global.mbarrier::complete_tx::bytes [%0], [%1, {%3, %4, %5}], [%2];"
               ::"r"(dst), "l"(m), "r"(bar), "r"(c0), "r"(c1), "r"(0) : "memory");
}
DEVI void tma2_mc(uint32_t dst, const CUtensorMap* m, int c0, int c1, uint32_t bar) {
  asm volatile("cp.async.bulk.tensor.2d.shared::cluster.global.mbarrier::complete_tx::bytes.multicast::cluster [%0], [%1, {%3, %4}], [%2], %5;"
               ::"r"(dst), "l"(m), "r"(bar), "r"(c0), "r"(c1), "h"((uint16_t)3) : "memory");
}
DEVI void tma3_mc(uint32_t dst, const CUtensorMap* m, int c0, int c1, uint32_t bar) {
  asm volatile("cp.async.bulk.tensor.3d.shared::cluster.global.mbarrier::complete_tx::bytes.multicast::cluster [%0], [%1, {%3, %4, %6}], [%2], %5;"
               ::"r"(dst), "l"(m), "r"(bar), "r"(c0), "r"(c1), "h"((uint16_t)3), "r"(0) : "memory");
}
DEVI void prefetch_l2(const void* p, uint32_t bytes) { asm volatile("cp.async.bulk.prefetch.L2.global [%0], %1;" ::"l"(p), "r"(bytes) : "memory"); }
DEVI void fence_async_smem() { asm volatile("fence.proxy.async.shared::cta;" ::: "memory"); }
template <int ID, int N> DEVI void bar_sync() { asm volatile("bar.sync %0, %1;" ::"n"(ID), "n"(N) : "memory"); }
DEVI void bar_wg(int wg) { if (wg) bar_sync<2, 128>(); else bar_sync<1, 128>(); }
DEVI uint4 ldg4(const void* p) { uint4 v; asm volatile("ld.relaxed.gpu.global.v4.u32 {%0,%1,%2,%3}, [%4];" : "=r"(v.x), "=r"(v.y), "=r"(v.z), "=r"(v.w) : "l"(p) : "memory"); return v; }
DEVI uint2 ldg2(const void* p) { uint2 v; asm volatile("ld.relaxed.gpu.global.v2.u32 {%0,%1}, [%2];" : "=r"(v.x), "=r"(v.y) : "l"(p) : "memory"); return v; }
DEVI void poll4(uint4& v, const void* p, uint32_t tag) {
  asm volatile("{\n.reg .pred p;\n.reg .b32 t;\nxor.b32 t, %0, %5;\nand.b32 t, t, 1;\nsetp.ne.u32 p, t, 0;\n@p ld.relaxed.gpu.global.v4.u32 {%0,%1,%2,%3}, [%4];\n}\n"
               : "+r"(v.x), "+r"(v.y), "+r"(v.z), "+r"(v.w) : "l"(p), "r"(tag) : "memory");
}
DEVI void poll2(uint32_t& x, uint32_t& y, const void* p, uint32_t tag) {
  asm volatile("{\n.reg .pred p;\n.reg .b32 t;\nxor.b32 t, %0, %3;\nand.b32 t, t, 1;\nsetp.ne.u32 p, t, 0;\n@p ld.relaxed.gpu.global.v2.u32 {%0,%1}, [%2];\n}\n"
               : "+r"(x), "+r"(y) : "l"(p), "r"(tag) : "memory");
}
DEVI void stg4(const void* p, uint32_t a, uint32_t b, uint32_t c, uint32_t d) { asm volatile("st.relaxed.gpu.global.v4.u32 [%0], {%1,%2,%3,%4};" ::"l"(p), "r"(a), "r"(b), "r"(c), "r"(d) : "memory"); }
DEVI void stg2(const void* p, uint32_t a, uint32_t b) { asm volatile("st.relaxed.gpu.global.v2.u32 [%0], {%1,%2};" ::"l"(p), "r"(a), "r"(b) : "memory"); }
DEVI void ldsm4(uint32_t addr, uint32_t& a, uint32_t& b, uint32_t& c, uint32_t& d) { asm volatile("ldmatrix.sync.aligned.m8n8.x4.shared.b16 {%0,%1,%2,%3}, [%4];" : "=r"(a), "=r"(b), "=r"(c), "=r"(d) : "r"(addr) : "memory"); }
DEVI void ldsm2(uint32_t addr, uint32_t& a, uint32_t& b) { asm volatile("ldmatrix.sync.aligned.m8n8.x2.shared.b16 {%0,%1}, [%2];" : "=r"(a), "=r"(b) : "r"(addr) : "memory"); }
DEVI void stsm4(uint32_t addr, uint32_t a, uint32_t b, uint32_t c, uint32_t d) { asm volatile("stmatrix.sync.aligned.m8n8.x4.shared.b16 [%0], {%1,%2,%3,%4};" ::"r"(addr), "r"(a), "r"(b), "r"(c), "r"(d) : "memory"); }
DEVI void mma16816(float (&d)[4], const uint4& a, uint32_t b0, uint32_t b1) {
  asm("mma.sync.aligned.m16n8k16.row.col.f32.bf16.bf16.f32 {%0,%1,%2,%3}, {%4,%5,%6,%7}, {%8,%9}, {%0,%1,%2,%3};"
      : "+f"(d[0]), "+f"(d[1]), "+f"(d[2]), "+f"(d[3]) : "r"(a.x), "r"(a.y), "r"(a.z), "r"(a.w), "r"(b0), "r"(b1));
}
DEVI void sts128(uint32_t addr, uint32_t a, uint32_t b, uint32_t c, uint32_t d) { asm volatile("st.shared.v4.u32 [%0], {%1,%2,%3,%4};" ::"r"(addr), "r"(a), "r"(b), "r"(c), "r"(d) : "memory"); }
DEVI void sts32(uint32_t addr, uint32_t v) { asm volatile("st.shared.u32 [%0], %1;" ::"r"(addr), "r"(v) : "memory"); }
DEVI uint32_t pack2(float lo, float hi) { uint32_t r; asm("cvt.rn.bf16x2.f32 %0, %1, %2;" : "=r"(r) : "f"(hi), "f"(lo)); return r; }
DEVI float bf_lo(uint32_t v) { return __uint_as_float(v << 16); }
DEVI float bf_hi(uint32_t v) { return __uint_as_float(v & 0xffff0000u); }
DEVI float ex2(float x) { float y; asm("ex2.approx.ftz.f32 %0, %1;" : "=f"(y) : "f"(x)); return y; }
DEVI float rcp(float x) { float y; asm("rcp.approx.ftz.f32 %0, %1;" : "=f"(y) : "f"(x)); return y; }
DEVI float rsq(float x) { float y; asm("rsqrt.approx.ftz.f32 %0, %1;" : "=f"(y) : "f"(x)); return y; }
DEVI float tanh_fast(float x) { float y; asm("tanh.approx.f32 %0, %1;" : "=f"(y) : "f"(x)); return y; }
DEVI uint32_t settag(uint32_t w, uint32_t tag) { return (w & ~1u) | tag; }
DEVI int opaque(int x) { asm volatile("" : "+r"(x)); return x; }
DEVI void spin_guard(int& n) { if (++n > 2000000) __trap(); }

constexpr uint32_t H128 = (1024 >> 4) | (1u << 30);
constexpr uint32_t H64 = (512 >> 4) | (2u << 30);
constexpr uint32_t SMEM_AT = 1024;
DEVI constexpr uint32_t dlo(uint32_t off, uint32_t lbo = 16) { return ((SMEM_AT + off) >> 4) | ((lbo >> 4) << 16); }
DEVI void wg_fence() { asm volatile("wgmma.fence.sync.aligned;" ::: "memory"); }
DEVI void wg_commit() { asm volatile("wgmma.commit_group.sync.aligned;" ::: "memory"); }
template <int N> DEVI void wg_wait() { asm volatile("wgmma.wait_group.sync.aligned %0;" ::"n"(N) : "memory"); }
template <int N> DEVI void pin(float (&d)[N]) {
#pragma unroll
  for (int i = 0; i < N; i++) asm volatile("" : "+f"(d[i])::"memory");
}

template <int N> DEVI void pin(uint32_t (&d)[N]) {
#pragma unroll
  for (int i = 0; i < N; i++) asm volatile("" : "+r"(d[i])::"memory");
}

template <uint32_t HB> DEVI void wgmma_ss_n128(float (&d)[64], uint32_t da, uint32_t db) {
  asm volatile("{\n.reg .b64 da, db;\nmov.b64 da, {%64, %66};\nmov.b64 db, {%65, %67};\nwgmma.mma_async.sync.aligned.m64n128k16.f32.bf16.bf16 {%0, %1, %2, %3, %4, %5, %6, %7, %8, %9, %10, %11, %12, %13, %14, %15, %16, %17, %18, %19, %20, %21, %22, %23, %24, %25, %26, %27, %28, %29, %30, %31, %32, %33, %34, %35, %36, %37, %38, %39, %40, %41, %42, %43, %44, %45, %46, %47, %48, %49, %50, %51, %52, %53, %54, %55, %56, %57, %58, %59, %60, %61, %62, %63}, da, db, 1, 1, 1, 0, 1;\n}\n"
    : "+f"(d[0]), "+f"(d[1]), "+f"(d[2]), "+f"(d[3]), "+f"(d[4]), "+f"(d[5]), "+f"(d[6]), "+f"(d[7]), "+f"(d[8]), "+f"(d[9]), "+f"(d[10]), "+f"(d[11]), "+f"(d[12]), "+f"(d[13]), "+f"(d[14]), "+f"(d[15]), "+f"(d[16]), "+f"(d[17]), "+f"(d[18]), "+f"(d[19]), "+f"(d[20]), "+f"(d[21]), "+f"(d[22]), "+f"(d[23]), "+f"(d[24]), "+f"(d[25]), "+f"(d[26]), "+f"(d[27]), "+f"(d[28]), "+f"(d[29]), "+f"(d[30]), "+f"(d[31]), "+f"(d[32]), "+f"(d[33]), "+f"(d[34]), "+f"(d[35]), "+f"(d[36]), "+f"(d[37]), "+f"(d[38]), "+f"(d[39]), "+f"(d[40]), "+f"(d[41]), "+f"(d[42]), "+f"(d[43]), "+f"(d[44]), "+f"(d[45]), "+f"(d[46]), "+f"(d[47]), "+f"(d[48]), "+f"(d[49]), "+f"(d[50]), "+f"(d[51]), "+f"(d[52]), "+f"(d[53]), "+f"(d[54]), "+f"(d[55]), "+f"(d[56]), "+f"(d[57]), "+f"(d[58]), "+f"(d[59]), "+f"(d[60]), "+f"(d[61]), "+f"(d[62]), "+f"(d[63])
    : "r"(da), "r"(db), "n"(H128), "n"(HB));
}
template <uint32_t HB> DEVI void wgmma_ss_n128_z(float (&d)[64], uint32_t da, uint32_t db) {
  asm volatile("{\n.reg .b64 da, db;\nmov.b64 da, {%64, %66};\nmov.b64 db, {%65, %67};\nwgmma.mma_async.sync.aligned.m64n128k16.f32.bf16.bf16 {%0, %1, %2, %3, %4, %5, %6, %7, %8, %9, %10, %11, %12, %13, %14, %15, %16, %17, %18, %19, %20, %21, %22, %23, %24, %25, %26, %27, %28, %29, %30, %31, %32, %33, %34, %35, %36, %37, %38, %39, %40, %41, %42, %43, %44, %45, %46, %47, %48, %49, %50, %51, %52, %53, %54, %55, %56, %57, %58, %59, %60, %61, %62, %63}, da, db, 0, 1, 1, 0, 1;\n}\n"
    : "=f"(d[0]), "=f"(d[1]), "=f"(d[2]), "=f"(d[3]), "=f"(d[4]), "=f"(d[5]), "=f"(d[6]), "=f"(d[7]), "=f"(d[8]), "=f"(d[9]), "=f"(d[10]), "=f"(d[11]), "=f"(d[12]), "=f"(d[13]), "=f"(d[14]), "=f"(d[15]), "=f"(d[16]), "=f"(d[17]), "=f"(d[18]), "=f"(d[19]), "=f"(d[20]), "=f"(d[21]), "=f"(d[22]), "=f"(d[23]), "=f"(d[24]), "=f"(d[25]), "=f"(d[26]), "=f"(d[27]), "=f"(d[28]), "=f"(d[29]), "=f"(d[30]), "=f"(d[31]), "=f"(d[32]), "=f"(d[33]), "=f"(d[34]), "=f"(d[35]), "=f"(d[36]), "=f"(d[37]), "=f"(d[38]), "=f"(d[39]), "=f"(d[40]), "=f"(d[41]), "=f"(d[42]), "=f"(d[43]), "=f"(d[44]), "=f"(d[45]), "=f"(d[46]), "=f"(d[47]), "=f"(d[48]), "=f"(d[49]), "=f"(d[50]), "=f"(d[51]), "=f"(d[52]), "=f"(d[53]), "=f"(d[54]), "=f"(d[55]), "=f"(d[56]), "=f"(d[57]), "=f"(d[58]), "=f"(d[59]), "=f"(d[60]), "=f"(d[61]), "=f"(d[62]), "=f"(d[63])
    : "r"(da), "r"(db), "n"(H128), "n"(HB));
}
template <uint32_t HB> DEVI void wgmma_ss_n192(float (&d)[96], uint32_t da, uint32_t db) {
  asm volatile("{\n.reg .b64 da, db;\nmov.b64 da, {%96, %98};\nmov.b64 db, {%97, %99};\nwgmma.mma_async.sync.aligned.m64n192k16.f32.bf16.bf16 {%0, %1, %2, %3, %4, %5, %6, %7, %8, %9, %10, %11, %12, %13, %14, %15, %16, %17, %18, %19, %20, %21, %22, %23, %24, %25, %26, %27, %28, %29, %30, %31, %32, %33, %34, %35, %36, %37, %38, %39, %40, %41, %42, %43, %44, %45, %46, %47, %48, %49, %50, %51, %52, %53, %54, %55, %56, %57, %58, %59, %60, %61, %62, %63, %64, %65, %66, %67, %68, %69, %70, %71, %72, %73, %74, %75, %76, %77, %78, %79, %80, %81, %82, %83, %84, %85, %86, %87, %88, %89, %90, %91, %92, %93, %94, %95}, da, db, 1, 1, 1, 0, 1;\n}\n"
    : "+f"(d[0]), "+f"(d[1]), "+f"(d[2]), "+f"(d[3]), "+f"(d[4]), "+f"(d[5]), "+f"(d[6]), "+f"(d[7]), "+f"(d[8]), "+f"(d[9]), "+f"(d[10]), "+f"(d[11]), "+f"(d[12]), "+f"(d[13]), "+f"(d[14]), "+f"(d[15]), "+f"(d[16]), "+f"(d[17]), "+f"(d[18]), "+f"(d[19]), "+f"(d[20]), "+f"(d[21]), "+f"(d[22]), "+f"(d[23]), "+f"(d[24]), "+f"(d[25]), "+f"(d[26]), "+f"(d[27]), "+f"(d[28]), "+f"(d[29]), "+f"(d[30]), "+f"(d[31]), "+f"(d[32]), "+f"(d[33]), "+f"(d[34]), "+f"(d[35]), "+f"(d[36]), "+f"(d[37]), "+f"(d[38]), "+f"(d[39]), "+f"(d[40]), "+f"(d[41]), "+f"(d[42]), "+f"(d[43]), "+f"(d[44]), "+f"(d[45]), "+f"(d[46]), "+f"(d[47]), "+f"(d[48]), "+f"(d[49]), "+f"(d[50]), "+f"(d[51]), "+f"(d[52]), "+f"(d[53]), "+f"(d[54]), "+f"(d[55]), "+f"(d[56]), "+f"(d[57]), "+f"(d[58]), "+f"(d[59]), "+f"(d[60]), "+f"(d[61]), "+f"(d[62]), "+f"(d[63]), "+f"(d[64]), "+f"(d[65]), "+f"(d[66]), "+f"(d[67]), "+f"(d[68]), "+f"(d[69]), "+f"(d[70]), "+f"(d[71]), "+f"(d[72]), "+f"(d[73]), "+f"(d[74]), "+f"(d[75]), "+f"(d[76]), "+f"(d[77]), "+f"(d[78]), "+f"(d[79]), "+f"(d[80]), "+f"(d[81]), "+f"(d[82]), "+f"(d[83]), "+f"(d[84]), "+f"(d[85]), "+f"(d[86]), "+f"(d[87]), "+f"(d[88]), "+f"(d[89]), "+f"(d[90]), "+f"(d[91]), "+f"(d[92]), "+f"(d[93]), "+f"(d[94]), "+f"(d[95])
    : "r"(da), "r"(db), "n"(H128), "n"(HB));
}
template <uint32_t HB> DEVI void wgmma_ss_n192_z(float (&d)[96], uint32_t da, uint32_t db) {
  asm volatile("{\n.reg .b64 da, db;\nmov.b64 da, {%96, %98};\nmov.b64 db, {%97, %99};\nwgmma.mma_async.sync.aligned.m64n192k16.f32.bf16.bf16 {%0, %1, %2, %3, %4, %5, %6, %7, %8, %9, %10, %11, %12, %13, %14, %15, %16, %17, %18, %19, %20, %21, %22, %23, %24, %25, %26, %27, %28, %29, %30, %31, %32, %33, %34, %35, %36, %37, %38, %39, %40, %41, %42, %43, %44, %45, %46, %47, %48, %49, %50, %51, %52, %53, %54, %55, %56, %57, %58, %59, %60, %61, %62, %63, %64, %65, %66, %67, %68, %69, %70, %71, %72, %73, %74, %75, %76, %77, %78, %79, %80, %81, %82, %83, %84, %85, %86, %87, %88, %89, %90, %91, %92, %93, %94, %95}, da, db, 0, 1, 1, 0, 1;\n}\n"
    : "=f"(d[0]), "=f"(d[1]), "=f"(d[2]), "=f"(d[3]), "=f"(d[4]), "=f"(d[5]), "=f"(d[6]), "=f"(d[7]), "=f"(d[8]), "=f"(d[9]), "=f"(d[10]), "=f"(d[11]), "=f"(d[12]), "=f"(d[13]), "=f"(d[14]), "=f"(d[15]), "=f"(d[16]), "=f"(d[17]), "=f"(d[18]), "=f"(d[19]), "=f"(d[20]), "=f"(d[21]), "=f"(d[22]), "=f"(d[23]), "=f"(d[24]), "=f"(d[25]), "=f"(d[26]), "=f"(d[27]), "=f"(d[28]), "=f"(d[29]), "=f"(d[30]), "=f"(d[31]), "=f"(d[32]), "=f"(d[33]), "=f"(d[34]), "=f"(d[35]), "=f"(d[36]), "=f"(d[37]), "=f"(d[38]), "=f"(d[39]), "=f"(d[40]), "=f"(d[41]), "=f"(d[42]), "=f"(d[43]), "=f"(d[44]), "=f"(d[45]), "=f"(d[46]), "=f"(d[47]), "=f"(d[48]), "=f"(d[49]), "=f"(d[50]), "=f"(d[51]), "=f"(d[52]), "=f"(d[53]), "=f"(d[54]), "=f"(d[55]), "=f"(d[56]), "=f"(d[57]), "=f"(d[58]), "=f"(d[59]), "=f"(d[60]), "=f"(d[61]), "=f"(d[62]), "=f"(d[63]), "=f"(d[64]), "=f"(d[65]), "=f"(d[66]), "=f"(d[67]), "=f"(d[68]), "=f"(d[69]), "=f"(d[70]), "=f"(d[71]), "=f"(d[72]), "=f"(d[73]), "=f"(d[74]), "=f"(d[75]), "=f"(d[76]), "=f"(d[77]), "=f"(d[78]), "=f"(d[79]), "=f"(d[80]), "=f"(d[81]), "=f"(d[82]), "=f"(d[83]), "=f"(d[84]), "=f"(d[85]), "=f"(d[86]), "=f"(d[87]), "=f"(d[88]), "=f"(d[89]), "=f"(d[90]), "=f"(d[91]), "=f"(d[92]), "=f"(d[93]), "=f"(d[94]), "=f"(d[95])
    : "r"(da), "r"(db), "n"(H128), "n"(HB));
}
template <uint32_t HB> DEVI void wgmma_rs_n32(float (&d)[16], uint32_t a0, uint32_t a1, uint32_t a2, uint32_t a3, uint32_t db) {
  asm volatile("{\n.reg .b64 db;\nmov.b64 db, {%20, %21};\nwgmma.mma_async.sync.aligned.m64n32k16.f32.bf16.bf16 {%0, %1, %2, %3, %4, %5, %6, %7, %8, %9, %10, %11, %12, %13, %14, %15}, {%16, %17, %18, %19}, db, 1, 1, 1, 1;\n}\n"
    : "+f"(d[0]), "+f"(d[1]), "+f"(d[2]), "+f"(d[3]), "+f"(d[4]), "+f"(d[5]), "+f"(d[6]), "+f"(d[7]), "+f"(d[8]), "+f"(d[9]), "+f"(d[10]), "+f"(d[11]), "+f"(d[12]), "+f"(d[13]), "+f"(d[14]), "+f"(d[15])
    : "r"(a0), "r"(a1), "r"(a2), "r"(a3), "r"(db), "n"(HB));
}
template <uint32_t HB> DEVI void wgmma_rs_n32_z(float (&d)[16], uint32_t a0, uint32_t a1, uint32_t a2, uint32_t a3, uint32_t db) {
  asm volatile("{\n.reg .b64 db;\nmov.b64 db, {%20, %21};\nwgmma.mma_async.sync.aligned.m64n32k16.f32.bf16.bf16 {%0, %1, %2, %3, %4, %5, %6, %7, %8, %9, %10, %11, %12, %13, %14, %15}, {%16, %17, %18, %19}, db, 0, 1, 1, 1;\n}\n"
    : "=f"(d[0]), "=f"(d[1]), "=f"(d[2]), "=f"(d[3]), "=f"(d[4]), "=f"(d[5]), "=f"(d[6]), "=f"(d[7]), "=f"(d[8]), "=f"(d[9]), "=f"(d[10]), "=f"(d[11]), "=f"(d[12]), "=f"(d[13]), "=f"(d[14]), "=f"(d[15])
    : "r"(a0), "r"(a1), "r"(a2), "r"(a3), "r"(db), "n"(HB));
}
template <uint32_t HB> DEVI void wgmma_rs_n56(float (&d)[28], uint32_t a0, uint32_t a1, uint32_t a2, uint32_t a3, uint32_t db) {
  asm volatile("{\n.reg .b64 db;\nmov.b64 db, {%32, %33};\nwgmma.mma_async.sync.aligned.m64n56k16.f32.bf16.bf16 {%0, %1, %2, %3, %4, %5, %6, %7, %8, %9, %10, %11, %12, %13, %14, %15, %16, %17, %18, %19, %20, %21, %22, %23, %24, %25, %26, %27}, {%28, %29, %30, %31}, db, 1, 1, 1, 1;\n}\n"
    : "+f"(d[0]), "+f"(d[1]), "+f"(d[2]), "+f"(d[3]), "+f"(d[4]), "+f"(d[5]), "+f"(d[6]), "+f"(d[7]), "+f"(d[8]), "+f"(d[9]), "+f"(d[10]), "+f"(d[11]), "+f"(d[12]), "+f"(d[13]), "+f"(d[14]), "+f"(d[15]), "+f"(d[16]), "+f"(d[17]), "+f"(d[18]), "+f"(d[19]), "+f"(d[20]), "+f"(d[21]), "+f"(d[22]), "+f"(d[23]), "+f"(d[24]), "+f"(d[25]), "+f"(d[26]), "+f"(d[27])
    : "r"(a0), "r"(a1), "r"(a2), "r"(a3), "r"(db), "n"(HB));
}
template <uint32_t HB> DEVI void wgmma_rs_n56_z(float (&d)[28], uint32_t a0, uint32_t a1, uint32_t a2, uint32_t a3, uint32_t db) {
  asm volatile("{\n.reg .b64 db;\nmov.b64 db, {%32, %33};\nwgmma.mma_async.sync.aligned.m64n56k16.f32.bf16.bf16 {%0, %1, %2, %3, %4, %5, %6, %7, %8, %9, %10, %11, %12, %13, %14, %15, %16, %17, %18, %19, %20, %21, %22, %23, %24, %25, %26, %27}, {%28, %29, %30, %31}, db, 0, 1, 1, 1;\n}\n"
    : "=f"(d[0]), "=f"(d[1]), "=f"(d[2]), "=f"(d[3]), "=f"(d[4]), "=f"(d[5]), "=f"(d[6]), "=f"(d[7]), "=f"(d[8]), "=f"(d[9]), "=f"(d[10]), "=f"(d[11]), "=f"(d[12]), "=f"(d[13]), "=f"(d[14]), "=f"(d[15]), "=f"(d[16]), "=f"(d[17]), "=f"(d[18]), "=f"(d[19]), "=f"(d[20]), "=f"(d[21]), "=f"(d[22]), "=f"(d[23]), "=f"(d[24]), "=f"(d[25]), "=f"(d[26]), "=f"(d[27])
    : "r"(a0), "r"(a1), "r"(a2), "r"(a3), "r"(db), "n"(HB));
}
template <uint32_t HB> DEVI void wgmma_rs_n128(float (&d)[64], uint32_t a0, uint32_t a1, uint32_t a2, uint32_t a3, uint32_t db) {
  asm volatile("{\n.reg .b64 db;\nmov.b64 db, {%68, %69};\nwgmma.mma_async.sync.aligned.m64n128k16.f32.bf16.bf16 {%0, %1, %2, %3, %4, %5, %6, %7, %8, %9, %10, %11, %12, %13, %14, %15, %16, %17, %18, %19, %20, %21, %22, %23, %24, %25, %26, %27, %28, %29, %30, %31, %32, %33, %34, %35, %36, %37, %38, %39, %40, %41, %42, %43, %44, %45, %46, %47, %48, %49, %50, %51, %52, %53, %54, %55, %56, %57, %58, %59, %60, %61, %62, %63}, {%64, %65, %66, %67}, db, 1, 1, 1, 1;\n}\n"
    : "+f"(d[0]), "+f"(d[1]), "+f"(d[2]), "+f"(d[3]), "+f"(d[4]), "+f"(d[5]), "+f"(d[6]), "+f"(d[7]), "+f"(d[8]), "+f"(d[9]), "+f"(d[10]), "+f"(d[11]), "+f"(d[12]), "+f"(d[13]), "+f"(d[14]), "+f"(d[15]), "+f"(d[16]), "+f"(d[17]), "+f"(d[18]), "+f"(d[19]), "+f"(d[20]), "+f"(d[21]), "+f"(d[22]), "+f"(d[23]), "+f"(d[24]), "+f"(d[25]), "+f"(d[26]), "+f"(d[27]), "+f"(d[28]), "+f"(d[29]), "+f"(d[30]), "+f"(d[31]), "+f"(d[32]), "+f"(d[33]), "+f"(d[34]), "+f"(d[35]), "+f"(d[36]), "+f"(d[37]), "+f"(d[38]), "+f"(d[39]), "+f"(d[40]), "+f"(d[41]), "+f"(d[42]), "+f"(d[43]), "+f"(d[44]), "+f"(d[45]), "+f"(d[46]), "+f"(d[47]), "+f"(d[48]), "+f"(d[49]), "+f"(d[50]), "+f"(d[51]), "+f"(d[52]), "+f"(d[53]), "+f"(d[54]), "+f"(d[55]), "+f"(d[56]), "+f"(d[57]), "+f"(d[58]), "+f"(d[59]), "+f"(d[60]), "+f"(d[61]), "+f"(d[62]), "+f"(d[63])
    : "r"(a0), "r"(a1), "r"(a2), "r"(a3), "r"(db), "n"(HB));
}
template <uint32_t HB> DEVI void wgmma_rs_n128_z(float (&d)[64], uint32_t a0, uint32_t a1, uint32_t a2, uint32_t a3, uint32_t db) {
  asm volatile("{\n.reg .b64 db;\nmov.b64 db, {%68, %69};\nwgmma.mma_async.sync.aligned.m64n128k16.f32.bf16.bf16 {%0, %1, %2, %3, %4, %5, %6, %7, %8, %9, %10, %11, %12, %13, %14, %15, %16, %17, %18, %19, %20, %21, %22, %23, %24, %25, %26, %27, %28, %29, %30, %31, %32, %33, %34, %35, %36, %37, %38, %39, %40, %41, %42, %43, %44, %45, %46, %47, %48, %49, %50, %51, %52, %53, %54, %55, %56, %57, %58, %59, %60, %61, %62, %63}, {%64, %65, %66, %67}, db, 0, 1, 1, 1;\n}\n"
    : "=f"(d[0]), "=f"(d[1]), "=f"(d[2]), "=f"(d[3]), "=f"(d[4]), "=f"(d[5]), "=f"(d[6]), "=f"(d[7]), "=f"(d[8]), "=f"(d[9]), "=f"(d[10]), "=f"(d[11]), "=f"(d[12]), "=f"(d[13]), "=f"(d[14]), "=f"(d[15]), "=f"(d[16]), "=f"(d[17]), "=f"(d[18]), "=f"(d[19]), "=f"(d[20]), "=f"(d[21]), "=f"(d[22]), "=f"(d[23]), "=f"(d[24]), "=f"(d[25]), "=f"(d[26]), "=f"(d[27]), "=f"(d[28]), "=f"(d[29]), "=f"(d[30]), "=f"(d[31]), "=f"(d[32]), "=f"(d[33]), "=f"(d[34]), "=f"(d[35]), "=f"(d[36]), "=f"(d[37]), "=f"(d[38]), "=f"(d[39]), "=f"(d[40]), "=f"(d[41]), "=f"(d[42]), "=f"(d[43]), "=f"(d[44]), "=f"(d[45]), "=f"(d[46]), "=f"(d[47]), "=f"(d[48]), "=f"(d[49]), "=f"(d[50]), "=f"(d[51]), "=f"(d[52]), "=f"(d[53]), "=f"(d[54]), "=f"(d[55]), "=f"(d[56]), "=f"(d[57]), "=f"(d[58]), "=f"(d[59]), "=f"(d[60]), "=f"(d[61]), "=f"(d[62]), "=f"(d[63])
    : "r"(a0), "r"(a1), "r"(a2), "r"(a3), "r"(db), "n"(HB));
}
template <uint32_t HB> DEVI void wgmma_ss_n32_ta(float (&d)[16], uint32_t da, uint32_t db) {
  asm volatile("{\n.reg .b64 da, db;\nmov.b64 da, {%16, %18};\nmov.b64 db, {%17, %19};\nwgmma.mma_async.sync.aligned.m64n32k16.f32.bf16.bf16 {%0, %1, %2, %3, %4, %5, %6, %7, %8, %9, %10, %11, %12, %13, %14, %15}, da, db, 1, 1, 1, 1, 1;\n}\n"
    : "+f"(d[0]), "+f"(d[1]), "+f"(d[2]), "+f"(d[3]), "+f"(d[4]), "+f"(d[5]), "+f"(d[6]), "+f"(d[7]), "+f"(d[8]), "+f"(d[9]), "+f"(d[10]), "+f"(d[11]), "+f"(d[12]), "+f"(d[13]), "+f"(d[14]), "+f"(d[15])
    : "r"(da), "r"(db), "n"(H128), "n"(HB));
}
template <uint32_t HB> DEVI void wgmma_ss_n32_ta_z(float (&d)[16], uint32_t da, uint32_t db) {
  asm volatile("{\n.reg .b64 da, db;\nmov.b64 da, {%16, %18};\nmov.b64 db, {%17, %19};\nwgmma.mma_async.sync.aligned.m64n32k16.f32.bf16.bf16 {%0, %1, %2, %3, %4, %5, %6, %7, %8, %9, %10, %11, %12, %13, %14, %15}, da, db, 0, 1, 1, 1, 1;\n}\n"
    : "=f"(d[0]), "=f"(d[1]), "=f"(d[2]), "=f"(d[3]), "=f"(d[4]), "=f"(d[5]), "=f"(d[6]), "=f"(d[7]), "=f"(d[8]), "=f"(d[9]), "=f"(d[10]), "=f"(d[11]), "=f"(d[12]), "=f"(d[13]), "=f"(d[14]), "=f"(d[15])
    : "r"(da), "r"(db), "n"(H128), "n"(HB));
}

struct Ring {
  uint32_t base;
  uint32_t rel_bar;
  uint32_t layer;
  DEVI void acquire(int n) const { mbar_wait_c(base + BAR_FULL + 8 * (n % NSLOT), ((n / NSLOT) & 1) ^ layer); }
  DEVI uint32_t addr(int n) const { return base + SM_RING + (n % NSLOT) * SLOT_BYTES; }
  DEVI uint32_t desc(int n, uint32_t lbo = 16) const { return dlo(SM_RING, lbo) + (n % NSLOT) * (SLOT_BYTES >> 4); }
  DEVI void release_slot(uint32_t s) const {
    asm volatile("{\n.reg .pred p;\nsetp.ne.u32 p, %0, 0;\n@p mbarrier.arrive.shared::cluster.b64 _, [%1];\n}\n" ::"r"(rel_bar), "r"(rel_bar + 8 * s) : "memory");
  }
  DEVI void release(int n) const { release_slot(n % NSLOT); }
};

DEVI void dual_softmax(const float (&p)[16], uint32_t (&o)[16], float f0, float f1) {
#pragma unroll
  for (int h = 0; h < 2; h++) {
    const float L2E = 1.4426950408889634f * (h ? f1 : f0);
    float v[7] = {p[2 * h], p[2 * h + 1], p[4 + 2 * h], p[5 + 2 * h], p[8 + 2 * h], p[9 + 2 * h], p[12 + 2 * h]};
    float mx = fmaxf(fmaxf(fmaxf(v[0], v[1]), fmaxf(v[2], v[3])), fmaxf(fmaxf(v[4], v[5]), v[6]));
    float mn = fminf(fminf(fminf(v[0], v[1]), fminf(v[2], v[3])), fminf(fminf(v[4], v[5]), v[6]));
    mx = fmaxf(mx, __shfl_xor_sync(~0u, mx, 1)); mn = fminf(mn, __shfl_xor_sync(~0u, mn, 1));
    mx = fmaxf(mx, __shfl_xor_sync(~0u, mx, 2)); mn = fminf(mn, __shfl_xor_sync(~0u, mn, 2));
    float a = -mx * L2E, b = mn * L2E, e[7], f[7];
#pragma unroll
    for (int i = 0; i < 7; i++) { e[i] = ex2(fmaf(v[i], L2E, a)); f[i] = ex2(fmaf(v[i], -L2E, b)); }
    float se = ((e[0] + e[1]) + (e[2] + e[3])) + ((e[4] + e[5]) + e[6]);
    float sf = ((f[0] + f[1]) + (f[2] + f[3])) + ((f[4] + f[5]) + f[6]);
    se += __shfl_xor_sync(~0u, se, 1); sf += __shfl_xor_sync(~0u, sf, 1);
    se += __shfl_xor_sync(~0u, se, 2); sf += __shfl_xor_sync(~0u, sf, 2);
    float re = rcp(se), rf = rcp(sf);
    o[0 + h] = pack2(e[0] * re, e[1] * re); o[2 + h] = pack2(e[2] * re, e[3] * re);
    o[4 + h] = pack2(e[4] * re, e[5] * re); o[6 + h] = pack2(e[6] * re, 0.f);
    o[8 + h] = pack2(f[0] * rf, f[1] * rf); o[10 + h] = pack2(f[2] * rf, f[3] * rf);
    o[12 + h] = pack2(f[4] * rf, f[5] * rf); o[14 + h] = pack2(f[6] * rf, 0.f);
  }
}

DEVI void project(uint32_t (&f)[14], float (&p0)[16], float (&p1)[16]) {
  pin(f);
  wg_fence();
  const uint32_t w = dlo(SM_WPHI);
  wgmma_rs_n32_z<H64>(p0, f[0], f[1], f[2], f[3], w);
  wgmma_rs_n32_z<H64>(p1, f[6], f[7], f[8], f[9], w + 128);
  wgmma_rs_n32<H64>(p0, f[4], f[5], f[6], f[7], w + 64);
  wgmma_rs_n32<H64>(p1, f[10], f[11], f[12], f[13], w + 192);
  wg_commit();
}

DEVI void pack_v(const float (&acc)[28], uint32_t (&vf)[16], int q, float f0, float f1) {
#pragma unroll
  for (int i = 0; i < 6; i++) {
    const float f = (i & 1) ? f1 : f0;
    vf[i] = pack2(acc[2 * i] * f, acc[2 * i + 1] * f); vf[10 + i] = pack2(acc[16 + 2 * i] * f, acc[17 + 2 * i] * f);
  }
  const uint32_t m0 = pack2(acc[12] * f0, acc[13] * f0), m1 = pack2(acc[14] * f1, acc[15] * f1), one = (q & 1) ? 0u : 0x3F80u;
  vf[6] = q < 2 ? m0 : one; vf[7] = q < 2 ? m1 : one; vf[8] = q < 2 ? one : m0; vf[9] = q < 2 ? one : m1;
}

struct Ptr { const char* p16; const char* p8; };
DEVI Ptr operator+(const Ptr& a, uint32_t o) { return Ptr{a.p16 + o, a.p8 + o}; }
DEVI uint32_t or_xor(uint32_t acc, uint32_t a, uint32_t t) { uint32_t r; asm("lop3.b32 %0, %1, %2, %3, 0xF6;" : "=r"(r) : "r"(acc), "r"(a), "r"(t)); return r; }
DEVI const char* after(const char* p, uint32_t w, uint32_t tag) {
  asm volatile("{\n.reg .b32 t;\n.reg .b64 u;\nxor.b32 t, %1, %2;\nand.b32 t, t, 1;\ncvt.u64.u32 u, t;\nadd.s64 %0, %0, u;\n}\n" : "+l"(p) : "r"(w), "r"(tag));
  return p;
}
DEVI Ptr after(const Ptr& p, uint32_t w, uint32_t tag) { return Ptr{after(p.p16, w, tag), after(p.p8, w, tag)}; }
constexpr uint32_t AGSRC = 16384;
DEVI void pair_load(uint4* X, const Ptr& p) {
  X[0] = ldg4(p.p16); X[1] = ldg4(p.p16 + 512); X[2] = ldg4(p.p16 + 1024);
  const uint2 a = ldg2(p.p8), b = ldg2(p.p8 + AGSRC);
  X[3] = make_uint4(a.x, a.y, b.x, b.y);
  X[4] = ldg4(p.p16 + AGSRC); X[5] = ldg4(p.p16 + AGSRC + 512); X[6] = ldg4(p.p16 + AGSRC + 1024);
}
DEVI void pair_poll(uint4* X, const Ptr& p, uint32_t tag) {
  poll4(X[0], p.p16, tag); poll4(X[1], p.p16 + 512, tag); poll4(X[2], p.p16 + 1024, tag);
  poll2(X[3].x, X[3].y, p.p8, tag); poll2(X[3].z, X[3].w, p.p8 + AGSRC, tag);
  poll4(X[4], p.p16 + AGSRC, tag); poll4(X[5], p.p16 + AGSRC + 512, tag); poll4(X[6], p.p16 + AGSRC + 1024, tag);
}
DEVI uint32_t pair_bad(const uint4* X, uint32_t tag) {
  uint32_t bad = X[3].z ^ tag;
#pragma unroll
  for (int t = 0; t < 7; t++) bad = or_xor(bad, X[t].x, tag);
  return bad;
}
template <int NP, bool STATS>
DEVI void gather(uint4* X, uint2 (&S)[8], const Ptr& p, const char* ps, uint32_t tag) {
  if (STATS) {
#pragma unroll
    for (int s = 0; s < 8; s++) S[s] = ldg2(ps + s * AGSRC);
  }
  pair_load(X, p);
  int n = 0;
  while (true) {
    uint32_t bad = pair_bad(X, tag);
    if (STATS) {
#pragma unroll
      for (int s = 0; s < 8; s++) bad = or_xor(bad, S[s].x, tag);
    }
    if (!__any_sync(~0u, bad & 1u)) break;
    if (STATS) {
#pragma unroll
      for (int s = 0; s < 8; s++) poll2(S[s].x, S[s].y, ps + s * AGSRC, tag);
    }
    pair_poll(X, p, tag);
    spin_guard(n);
  }
  const Ptr p1 = after(p, X[0].x, tag);
#pragma unroll
  for (int m = 1; m < NP; m++) pair_load(X + 7 * m, p1 + m * 2 * AGSRC);
}
DEVI void pair_wait(uint4* X, const Ptr& p, uint32_t tag) {
  int n = 0;
  while (__any_sync(~0u, pair_bad(X, tag) & 1u)) { pair_poll(X, p, tag); spin_guard(n); }
}
DEVI void send(const Ptr& p, const uint32_t (&d)[14], uint32_t tag) {
  stg4(p.p16, settag(d[0], tag), d[1], d[2], d[3]); stg4(p.p16 + 512, settag(d[4], tag), d[5], d[6], d[7]);
  stg4(p.p16 + 1024, settag(d[8], tag), d[9], d[10], d[11]); stg2(p.p8, settag(d[12], tag), d[13]);
}
DEVI void pack28(const float (&v)[28], uint32_t (&d)[14]) {
#pragma unroll
  for (int i = 0; i < 14; i++) d[i] = pack2(v[2 * i], v[2 * i + 1]);
}
DEVI void publish(const Ptr& p, const uint32_t (&d)[14], bool odd, uint32_t tag) {
  uint32_t e[14];
#pragma unroll
  for (int i = 0; i < 14; i++) e[i] = odd ? d[(i + 2) % 14] : d[i];
  send(p, e, tag);
}
DEVI void publish_stats(const char* p, const float (&v)[28], uint32_t tag, int lane) {
  float sa[4], qa[4];
#pragma unroll
  for (int e = 0; e < 4; e++) {
    sa[e] = ((v[e] + v[4 + e]) + (v[8 + e] + v[12 + e])) + ((v[16 + e] + v[20 + e]) + v[24 + e]);
    qa[e] = fmaf(v[e], v[e], fmaf(v[4 + e], v[4 + e], fmaf(v[8 + e], v[8 + e], v[12 + e] * v[12 + e]))) +
            fmaf(v[16 + e], v[16 + e], fmaf(v[20 + e], v[20 + e], v[24 + e] * v[24 + e]));
  }
  const float s0 = sa[0] + sa[1], s1 = sa[2] + sa[3], q0 = qa[0] + qa[1], q1 = qa[2] + qa[3];
  float s = (lane & 2) ? s1 : s0, q = (lane & 2) ? q1 : q0;
  s += __shfl_xor_sync(~0u, (lane & 2) ? s0 : s1, 2); q += __shfl_xor_sync(~0u, (lane & 2) ? q0 : q1, 2);
  s += __shfl_xor_sync(~0u, s, 1); q += __shfl_xor_sync(~0u, q, 1);
  if (!(lane & 1)) stg2(p, settag(__float_as_uint(q), tag), __float_as_uint(s));
}
struct Norm { uint32_t r0, b0, r1, b1; float f0, f1; };
DEVI Norm make_norm(float m0, float rs0, float m1, float rs1) {
  Norm n;
  n.r0 = pack2(rs0, rs0); n.r1 = pack2(rs1, rs1);
  const float h0 = bf_lo(n.r0), h1 = bf_lo(n.r1);
  n.b0 = pack2(-m0 * h0, -m0 * h0); n.b1 = pack2(-m1 * h1, -m1 * h1);
  n.f0 = rs0 * rcp(h0); n.f1 = rs1 * rcp(h1);
  return n;
}
DEVI Norm combine_stats(const uint2 (&S)[8], int lane) {
  float m = 0.f, q = 0.f;
#pragma unroll
  for (int s = 0; s < 8; s++) { m += __uint_as_float(S[s].y); q += __uint_as_float(S[s].x); }
  m *= 1.f / 448.f;
  const float r = rsq(fmaxf(q * (1.f / 448.f) - m * m, 0.f) + 1e-5f);
  const float ro = __shfl_xor_sync(~0u, r, 2), mo = __shfl_xor_sync(~0u, m, 2);
  const bool lo = !(lane & 2);
  return make_norm(lo ? m : mo, lo ? r : ro, lo ? mo : m, lo ? ro : r);
}
DEVI uint32_t norm2(uint32_t v, uint32_t r, uint32_t b) { uint32_t y; asm("fma.rn.bf16x2 %0, %1, %2, %3;" : "=r"(y) : "r"(v), "r"(r), "r"(b)); return y; }
DEVI void norm_step(uint4& v, const Norm& n, uint32_t ax, int s) {
  v.x = norm2(v.x, n.r0, n.b0); v.y = norm2(v.y, n.r1, n.b1); v.z = norm2(v.z, n.r0, n.b0); v.w = norm2(v.w, n.r1, n.b1);
  stsm4((ax ^ ((s & 3) << 5)) + (s >> 2) * 16384, v.x, v.y, v.z, v.w);
}

struct Act { float c1[2], c2[2], c3[2]; };
DEVI Act make_act(float f0, float f1) {
  constexpr float C1 = 0.7978845608028654f, C3 = 0.044715f * 0.7978845608028654f;
  Act a = {{C1 * f0, C1 * f1}, {0.5f * f0 * f0, 0.5f * f1 * f1}, {C3 * f0 * f0 * f0, C3 * f1 * f1 * f1}};
  asm volatile("" : "+f"(a.c1[0]), "+f"(a.c1[1]), "+f"(a.c2[0]), "+f"(a.c2[1]), "+f"(a.c3[0]), "+f"(a.c3[1]));
  return a;
}
template <int NH>
DEVI void geglu(const float (&acc)[NH], uint32_t* h, const Act& c, int i0) {
#pragma unroll
  for (int i = i0; i < i0 + 8; i += 2) {
    const int row = (i >> 1) & 1;
    float r[2];
#pragma unroll
    for (int e = 0; e < 2; e++) {
      const float g = acc[i + e], u = acc[NH / 2 + i + e];
      const float t = tanh_fast(g * fmaf(g * g, c.c3[row], c.c1[row]));
      const float hu = (c.c2[row] * g) * u;
      r[e] = fmaf(hu, t, hu);
    }
    h[i / 2] = pack2(r[0], r[1]);
  }
}

DEVI constexpr int dn_chunk(int t) { return t < 4 ? t >> 1 : t < 8 ? t & 1 : t >> 2; }
DEVI constexpr int dn_part(int t) { return t < 4 ? t & 1 : t < 8 ? t >> 1 : t & 3; }
DEVI void dn_coords(int t, int j, int cta, int& col, int& row) {
  const int p = dn_part(t);
  col = 56 * ((j + 2 + 2 * dn_chunk(t)) & 7);
  row = 224 * (j ^ (p >> 1)) + (p & 1) * 112 + cta * 56;
}

__global__ void __launch_bounds__(384, 1)
fused_kernel(const __grid_constant__ Maps maps, const __nv_bfloat16* __restrict__ wqkv_g, const __nv_bfloat16* __restrict__ wphi_g, const __nv_bfloat16* __restrict__ wo_g,
             const __nv_bfloat16* __restrict__ wg_g, const __nv_bfloat16* __restrict__ wu_g, const __nv_bfloat16* __restrict__ wd_g,
             __nv_bfloat16* __restrict__ out, const int zero) {
  extern __shared__ __align__(1024) uint8_t smem_raw[];
  const uint32_t base = smem_u32(smem_raw);
  if ((base & 0xFFFFFF) != SMEM_AT) __trap();
  const int tid = threadIdx.x, warp = tid >> 5, lane = tid & 31;
  const int cta = blockIdx.x & 1, j = blockIdx.x >> 4, r = blockIdx.x & 15;
  if (warp == 8) {
    if (lane == 0) {
#pragma unroll
      for (int i = 0; i < 4; i++) mbar_init(base + BAR_X + 8 * i, 1);
      fence_async_smem();
#pragma unroll
      for (int i = 0; i < 4; i++) {
        mbar_expect_tx(base + BAR_X + 8 * i, i < 3 ? 32768 : 16384);
        tma3(base + SM_A + i * 32768, &maps.x, i * 128, r * 128, base + BAR_X + 8 * i);
        if (i < 3) tma3(base + SM_A + i * 32768 + 16384, &maps.x, i * 128 + 64, r * 128, base + BAR_X + 8 * i);
      }
    }
    __syncwarp();
    asm volatile("bar.arrive 0, 384;" ::: "memory");
  } else {
    if (tid == 288) {
#pragma unroll
      for (int i = 0; i < NSLOT; i++) mbar_init(base + BAR_FULL + 8 * i, 1);
#pragma unroll
      for (int i = 0; i < NSLOT + 1; i++) mbar_init(base + BAR_EMPTY + 8 * i, 4);
#pragma unroll
      for (int i = 0; i < 8; i++) mbar_init(base + BAR_W + 8 * i, 1);
      mbar_init(base + BAR_AUX, 2);
      mbar_init(base + BAR_PUB, 8);
      mbar_init(base + BAR_GO, 1);
      asm volatile("fence.mbarrier_init.release.cluster;" ::: "memory");
      fence_async_smem();
    }
    __syncwarp();
    bar_sync<0, 384>();
  }
  asm volatile("barrier.cluster.arrive.relaxed.aligned;" ::: "memory");
  if (warp >= 8) {
    asm volatile("setmaxnreg.dec.sync.aligned.u32 56;");
    asm volatile("barrier.cluster.wait.aligned;" ::: "memory");
    if (warp < 10) {
      const int pw = __shfl_sync(~0u, warp - 8, 0);
      uint32_t slot = pw, phase = 1;
#pragma unroll 1
      for (int n = pw; n < TOTAL_STAGES; n += 2) {
        const int m = n >= STAGES_PER_LAYER ? n - STAGES_PER_LAYER : n;
        const uint32_t full = base + BAR_FULL + 8 * slot;
        const bool up = m >= 18 && m < 46;
        int map = 8, col = 56 * j, row, half = 7168, bytes = 12544;
        if (up) {
          const int wide = m >= 25 && m < 39, last = m >= 39;
          map = 4 + cta * 2 + wide; col = 224 * j + wide * 64 + last * 160; row = wide ? (m - 25) * 32 : (m - (last ? 39 : 18)) * 64; half = wide ? 6144 : 8192; bytes = 2 * half;
        }
        else if (m < 7) { map = 1; col += 448 + cta * 448; row = m * 64; half = 8192; bytes = 14336; }
        else if (m < 18) { map = m < 14 ? 2 : 3; row = ((m - 10) & 3) * 112 + cta * 56; }
        else dn_coords(m < 52 ? m - 46 : m - 38, j, cta, col, row);
        if (m >= 7 && m < 10) bytes = 0;
        const uint32_t dst = base + SM_RING + slot * SLOT_BYTES + cta * half;
        const CUtensorMap* mp = &maps.x + map;
        if (n == 2 || n == 3) mbar_wait(base + BAR_X + 16, 0);
        mbar_wait(base + BAR_EMPTY + 8 * slot, phase);
        if (elect()) {
          mbar_expect_tx(full, bytes);
          if (up) tma3_mc(dst, mp, col, row, full);
          else if (bytes) tma2_mc(dst, mp, col, row, full);
        }
        __syncwarp();
        slot += 2;
        if (slot >= NSLOT) { slot -= NSLOT; phase ^= 1; }
      }
    } else {
      const int t64 = tid - 320;
      if (t64 == 32) prefetch_l2((const char*)wqkv_g + blockIdx.x * 9408, 9408);
      const uint32_t par = *(volatile uint32_t*)&g_parity;
      if (t64 == 0) sts32(base + SM_PAR, par);
      {
        const int k = t64 & 31, d = k - 4 * (t64 >> 5);
        uint2 v[7] = {};
        if (d >= 0 && d < 28) {
#pragma unroll
          for (int i = 0; i < 7; i++) v[i] = __ldg((const uint2*)wphi_g + ((2 * j + (t64 >> 5)) * 28 + d) * 7 + i);
        }
        const uint32_t row = base + SM_WPHI + t64 * 64 + (((k >> 1) & 3) << 4);
#pragma unroll
        for (int c = 0; c < 3; c++) sts128(row ^ (c << 4), v[2 * c].x, v[2 * c].y, v[2 * c + 1].x, v[2 * c + 1].y);
        sts128(row ^ 48, v[6].x & 0xffffu, v[6].x >> 16, v[6].y & 0xffffu, v[6].y >> 16);
      }
      const char* o1 = (const char*)g_ag + (uint32_t)(AGBUF + (r * 8 + j) * AGSRC + t64 * 16);
#pragma unroll 1
      for (int i = 0; i < 8; i++) stg4(g_kv1 + (uint32_t)(((j * 16 + 2 * i + (t64 >> 5)) * 16 + r) * 32 + lane), 0, 0, 0, 0);
      stg2((const char*)(g_kv2 + j * 512 + r * 32) + t64 * 8, 0, 0);
#pragma unroll 2
      for (int i = 0; i < 16; i++) stg4(o1 - AGBUF + i * 1024, par, par, par, par);
      fence_async_smem();
      __syncwarp();
      if (lane == 0) mbar_arrive(base + BAR_AUX);
      {
        const char* ph = (const char*)g_h + (uint32_t)((r * 8 + j) * HSRC + 5120 + t64 * 16);
#pragma unroll 1
        for (int i = 0; i < 8; i++) {
          stg4(ph + i * 7168, 0, 0, 0, 0); stg4(ph + i * 7168 + 1024, 0, 0, 0, 0);
        }
#pragma unroll 1
        for (int c = 0; c < 3; c++) {
          const char* pq = (const char*)g_part + (uint32_t)(((r * 8 + ((j + 2 + 2 * c) & 7)) * 3 + c) * PSRC + t64 * 16);
#pragma unroll 2
          for (int i = 0; i < 14; i++) stg4(pq + i * 1024, 0, 0, 0, 0);
        }
      }
      mbar_wait(base + BAR_GO, 0);
#pragma unroll 2
      for (int i = 0; i < 16; i++) stg4(o1 + i * 1024, 0, 0, 0, 0);
      __syncwarp();
      if (lane == 0) {
        if (warp == 10) { prefetch_l2((const char*)wo_g + blockIdx.x * 3136, 3136); prefetch_l2((const char*)wg_g + blockIdx.x * 12544, 12544); }
        else { prefetch_l2((const char*)wu_g + blockIdx.x * 12544, 12544); prefetch_l2((const char*)wd_g + blockIdx.x * 12544, 12544); }
      }
      __syncwarp();
#pragma unroll 1
      for (int layer = 0; layer < 2; layer++) {
        const uint32_t tag = layer ^ 1;
        mbar_wait(base + BAR_PUB, layer);
        {
          uint2 v[16];
          const char* src = (const char*)(g_kv1 + (j * 16 + r) * 512) + t64 * 8;
#pragma unroll
          for (int s = 0; s < 16; s++) v[s] = ldg2(src + s * 512);
          int n = 0;
          while (true) {
            uint32_t bad = 0;
#pragma unroll
            for (int s = 0; s < 16; s++) bad = or_xor(bad, v[s].x, tag);
            if (!(bad & 1u)) break;
#pragma unroll
            for (int s = 0; s < 16; s++) poll2(v[s].x, v[s].y, src + s * 512, tag);
            spin_guard(n);
          }
          float a = 0.f, b = 0.f, c = 0.f, d = 0.f;
#pragma unroll
          for (int s = 0; s < 16; s++) { a += bf_lo(v[s].x); b += bf_hi(v[s].x); c += bf_lo(v[s].y); d += bf_hi(v[s].y); }
          stg2((const char*)(g_kv2 + j * 512 + r * 32) + t64 * 8, settag(pack2(a, b), tag), pack2(c, d));
        }
        {
          uint4 v[8];
          const uint4* src = g_kv2 + j * 512 + t64;
#pragma unroll
          for (int u = 0; u < 8; u++) v[u] = ldg4(src + u * 64);
          int n = 0;
          while (true) {
            uint32_t bad = 0;
#pragma unroll
            for (int u = 0; u < 8; u++) bad = or_xor(or_xor(bad, v[u].x, tag), v[u].z, tag);
            if (!__any_sync(~0u, bad & 1u)) break;
#pragma unroll
            for (int u = 0; u < 8; u++) v[u] = ldg4(src + u * 64);
            spin_guard(n);
          }
          const uint32_t ka = base + SM_KVB + (warp - 10) * 1024 + (lane & 15) * 64 + (((lane >> 4) ^ ((lane >> 1) & 3)) << 4);
#pragma unroll
          for (int u = 0; u < 8; u++) stsm4((ka ^ ((u >> 2) << 5)) + (u & 3) * 2048, v[u].x, v[u].y, v[u].z, v[u].w);
          fence_async_smem();
          __syncwarp();
          if (lane == 0) mbar_arrive(base + BAR_AUX);
        }
        if (t64 == 0) {
          mbar_wait(base + BAR_EMPTY + 8 * AFREE, layer);
          const long long t0 = clock64();
#pragma unroll 1
          for (int i = 0; i < 8; i++) {
            if (PD1 && i >= PN0) while (clock64() - t0 < PD1 + (i - PN0) * PD2) {}
            int col, row;
            dn_coords(6 + i, j, cta, col, row);
            mbar_expect_tx(base + BAR_W + 8 * i, 12544);
            tma2_mc(base + SM_A + i * 14336 + cta * 7168, &maps.dn, col, row, base + BAR_W + 8 * i);
          }
        }
        __syncwarp();
      }
    }
  } else {
    asm volatile("setmaxnreg.inc.sync.aligned.u32 224;");
    const int wg = __shfl_sync(~0u, warp >> 2, 0), q = lane & 3;
    Ring ring;
    ring.base = base;
    ring.rel_bar = (tid & 127) == 0 ? mapa(base + BAR_EMPTY, cta) : (tid & 127) == 32 ? mapa(base + BAR_EMPTY, cta ^ 1) : 0;
    const uint32_t rx = (warp * 16 + ((lane >> 3) & 1) * 8 + (lane & 7)) * 128 + (((lane >> 4) ^ (lane & 7)) << 4);
    const uint32_t ax = base + SM_A + rx, a0 = dlo(SM_A) + wg * 512;
    const uint32_t agoff = (r * 64 + warp) * 2048;
    auto ag_ptr = [&](int buf) { const char* b = (const char*)g_ag + (buf * AGBUF + agoff); return Ptr{b + lane * 16, b + 1536 + lane * 8}; };
    auto ag_stats = [&](int buf) { return (const char*)g_ag + (buf * AGBUF + agoff + 1792 + (lane >> 1) * 8); };
    float res[28];
    auto parity = [&]() { uint32_t v; asm volatile("ld.shared.u32 %0, [%1];" : "=r"(v) : "r"(base + SM_PAR)); return v; };

#pragma unroll 1
    for (int layer = 0; layer < 2; layer++) {
      const uint32_t tag = layer ^ 1;
      ring.layer = layer;

      uint32_t phq[2][16];
      {
        uint4 X[28];
        Norm nrm;
        uint32_t par = 0;
        const Ptr xp = ag_ptr(0);
        if (!layer) {
          float sm[4] = {}, d0[4] = {}, d1[4] = {}, sn[4] = {}, e0[4] = {}, e1[4] = {};
#pragma unroll
          for (int s = 0; s < 28; s++) {
            if ((s & 7) == 0) {
              mbar_wait_c(base + BAR_X + s, 0);
            }
            ldsm4((ax ^ ((s & 3) << 5)) + (s >> 2) * 16384, X[s].x, X[s].y, X[s].z, X[s].w);
            mma16816((s & 1) ? sn : sm, X[s], 0x3F803F80u, 0x3F803F80u);
            mma16816((s & 1) ? e0 : d0, X[s], X[s].x, X[s].z);
            mma16816((s & 1) ? e1 : d1, X[s], X[s].y, X[s].w);
          }
#pragma unroll
          for (int i = 0; i < 7; i++) {
            const int G = 7 * j + i;
            uint32_t a, b;
            ldsm2((ax & ~127u) + (G >> 3) * 16384 + (((G ^ lane) & 7) << 4), a, b);
            res[4 * i] = bf_lo(a); res[4 * i + 1] = bf_hi(a); res[4 * i + 2] = bf_lo(b); res[4 * i + 3] = bf_hi(b);
          }
          asm volatile("barrier.cluster.wait.aligned;" ::: "memory");
          const int g = lane >> 2, dl = g * 4 + (g >> 1);
          const float q0 = __shfl_sync(~0u, (g & 1) ? d0[1] + e0[1] : d0[0] + e0[0], dl), q1 = __shfl_sync(~0u, (g & 1) ? d1[3] + e1[3] : d1[2] + e1[2], dl);
          const float s0 = (sm[0] + sn[0]) * (1.f / 448.f), s1 = (sm[2] + sn[2]) * (1.f / 448.f);
          nrm = make_norm(s0, rsq(fmaxf(q0 * (1.f / 448.f) - s0 * s0, 0.f) + 1e-5f), s1, rsq(fmaxf(q1 * (1.f / 448.f) - s1 * s1, 0.f) + 1e-5f));
        } else {
          uint2 S[8];
          par = parity();
          gather<2, true>(X, S, xp, ag_stats(0), par);
          ring.release(52); ring.release(53);
          nrm = combine_stats(S, lane);
#pragma unroll
          for (int s = 14; s < 28; s++) X[s] = make_uint4(0, 0, 0, 0);
          if (wg) bar_sync<4, 256>(); else bar_sync<5, 256>();
        }
        const float f0 = nrm.f0, f1 = nrm.f1;
        uint32_t kf[14], vf[16];
        {
          float ak[28], av[28];
#pragma unroll
          for (int s = 0; s < 28; s++) {
            if (s % 7 == 0 && s && layer) pair_wait(X + s, xp + (s / 7) * 2 * AGSRC, par);
            norm_step(X[s], nrm, ax, s);
            if ((s == 7 || s == 14) && layer) pair_load(X + s + 7, after(xp, X[s].x & zero, 0) + (s / 7 + 1) * 2 * AGSRC);
            if ((s & 3) == 0) ring.acquire(s >> 2);
            if (s == 24 && !layer && tid == 0) mbar_arrive(base + BAR_GO);
            wg_fence();
            if (s == 0) {
              wgmma_rs_n56_z<H128>(ak, X[s].x, X[s].y, X[s].z, X[s].w, ring.desc(0));
              wgmma_rs_n56_z<H128>(av, X[s].x, X[s].y, X[s].z, X[s].w, ring.desc(0) + 512);
            } else {
              wgmma_rs_n56<H128>(ak, X[s].x, X[s].y, X[s].z, X[s].w, ring.desc(s >> 2) + (s & 3) * 128);
              wgmma_rs_n56<H128>(av, X[s].x, X[s].y, X[s].z, X[s].w, ring.desc(s >> 2) + (s & 3) * 128 + 512);
            }
            wg_commit();
            if ((s & 3) == 0 && s) { wg_wait<1>(); ring.release((s >> 2) - 1); }
          }
          ring.acquire(7); ring.acquire(8);
          wg_wait<0>();
          ring.release(6);
          pin(ak); pin(av);
          pack28(ak, kf);
          pack_v(av, vf, q, f0, f1);
        }
        if (!layer) mbar_wait_c(base + BAR_AUX, 0);
        ring.acquire(9);
#pragma unroll
        for (int k = 0; k < 4; k++) stsm4(ring.addr(9) + (rx ^ (k << 5)), vf[4 * k], vf[4 * k + 1], vf[4 * k + 2], vf[4 * k + 3]);
#pragma unroll
        for (int i = 0; i < 16; i++) phq[0][i] = phq[1][i] = 0;
#pragma unroll 1
        for (int ph = zero; ph < 2; ph++) {
          float p0[16], p1[16];
          project(kf, p0, p1);
          wg_wait<0>();
          pin(p0); pin(p1);
          dual_softmax(p0, phq[0], f0, f1);
          dual_softmax(p1, phq[1], f0, f1);
          if (ph) continue;
#pragma unroll
          for (int h = 0; h < 2; h++) {
            const uint32_t* o = phq[h];
#pragma unroll
            for (int k = 0; k < 4; k++) stsm4(ring.addr(7 + h) + (rx ^ (k << 5)), o[4 * k], o[4 * k + 1], o[4 * k + 2], o[4 * k + 3]);
          }
          fence_async_smem();
          bar_sync<3, 256>();
          float kv[16];
          wg_fence();
          {
            const uint32_t a = ring.desc(7) + wg * (SLOT_BYTES >> 4), b = ring.desc(9) + wg * 4;
#pragma unroll
            for (int k = 0; k < 8; k++) {
              if (k == 0) wgmma_ss_n32_ta_z<H128>(kv, a, b);
              else wgmma_ss_n32_ta<H128>(kv, a + k * 128, b + k * 128);
            }
          }
          wg_commit();
          wg_wait<0>();
          pin(kv);
          {
            const uint4* dst = g_kv1 + (uint32_t)(((j * 16 + opaque(warp)) * 16 + r) * 32 + lane);
#pragma unroll
            for (int k = 0; k < 2; k++)
              stg4(dst + k * 4096, settag(pack2(kv[8 * k], kv[8 * k + 1]), tag), pack2(kv[8 * k + 2], kv[8 * k + 3]),
                   settag(pack2(kv[8 * k + 4], kv[8 * k + 5]), tag), pack2(kv[8 * k + 6], kv[8 * k + 7]));
          }
          if (lane == 0) mbar_arrive(base + BAR_PUB);
          ring.release(7);
          ring.release(8); ring.release(9);
          float qa[28];
          uint4 Y[2][7];
          auto fetch = [&](int st) {
#pragma unroll
            for (int k = 0; k < 7; k++) { const int s = st * 7 + k; uint4& v = Y[st & 1][k]; ldsm4((ax ^ ((s & 3) << 5)) + (s >> 2) * 16384, v.x, v.y, v.z, v.w); }
          };
          fetch(0);
#pragma unroll
          for (int st = 0; st < 4; st++) {
            ring.acquire(10 + st);
            const uint32_t b = ring.desc(10 + st);
            wg_fence();
#pragma unroll
            for (int k = 0; k < 7; k++) {
              const uint4& v = Y[st & 1][k];
              if (st + k == 0) wgmma_rs_n56_z<H128>(qa, v.x, v.y, v.z, v.w, b); else wgmma_rs_n56<H128>(qa, v.x, v.y, v.z, v.w, b + k * 128);
            }
            wg_commit();
            if (st) { wg_wait<1>(); ring.release(9 + st); }
            if (st < 3) fetch(st + 1);
          }
          wg_wait<0>();
          ring.release(13);
          pin(qa);
          pack28(qa, kf);
#pragma unroll
          for (int i = 0; i < 16; i++) phq[0][i] = phq[1][i] = 0;
        }
      }
      const uint32_t otag = layer ? 0 : parity() ^ 1;
      {
        pin(phq[0]); pin(phq[1]);
        mbar_wait_c(base + BAR_AUX, (layer + 1) & 1);
        if (SKEW && wg) { const long long t0 = clock64(); while (clock64() - t0 < SKEW) {} }
        float n0[16], n1[16];
        const uint32_t kb = dlo(SM_KVB);
        wg_fence();
        wgmma_rs_n32_z<H64>(n0, phq[0][0], phq[0][1], phq[0][2], phq[0][3], kb);
        wgmma_rs_n32_z<H64>(n1, phq[1][0], phq[1][1], phq[1][2], phq[1][3], kb + 256);
#pragma unroll
        for (int k = 1; k < 4; k++) {
          wgmma_rs_n32<H64>(n0, phq[0][4 * k], phq[0][4 * k + 1], phq[0][4 * k + 2], phq[0][4 * k + 3], kb + k * 64);
          wgmma_rs_n32<H64>(n1, phq[1][4 * k], phq[1][4 * k + 1], phq[1][4 * k + 2], phq[1][4 * k + 3], kb + 256 + k * 64);
        }
        wg_commit();
        wg_wait<0>();
        pin(n0); pin(n1);
        const float ra = rcp(__shfl_sync(~0u, n0[12], (lane & ~3) | 2) + 1e-6f), rb = rcp(__shfl_sync(~0u, n0[14], (lane & ~3) | 2) + 1e-6f);
        const float rc = rcp(__shfl_sync(~0u, n1[0], lane & ~3) + 1e-6f), rd = rcp(__shfl_sync(~0u, n1[2], lane & ~3) + 1e-6f);
        uint32_t o[14];
#pragma unroll
        for (int i = 0; i < 6; i++) {
          o[i] = pack2(n0[2 * i] * ((i & 1) ? rb : ra), n0[2 * i + 1] * ((i & 1) ? rb : ra));
          o[8 + i] = pack2(n1[4 + 2 * i] * ((i & 1) ? rd : rc), n1[5 + 2 * i] * ((i & 1) ? rd : rc));
        }
        o[6] = q < 2 ? pack2(n0[12] * ra, n0[13] * ra) : pack2(n1[0] * rc, n1[1] * rc);
        o[7] = q < 2 ? pack2(n0[14] * rb, n0[15] * rb) : pack2(n1[2] * rd, n1[3] * rd);
        publish(ag_ptr(layer) + j * AGSRC, o, j & 1, otag);
        if (!(lane & 1)) stg2(ag_stats(layer) + j * AGSRC, otag, 0);
      }
      uint32_t rp[14];
      const uint32_t xtag = layer ? parity() ^ 1 : 1;
      {
        const Ptr op = ag_ptr(layer);
        uint4 X[28];
        { uint2 S[8]; gather<3, false>(X, S, op, ag_stats(layer), otag); }
        pin(res);
#pragma unroll
        for (int m = 0; m < 4; m++) {
          if (m == 1) {
            int n = 0;
            while (__any_sync(~0u, (pair_bad(X + 7, otag) | pair_bad(X + 14, otag)) & 1u)) {
              pair_poll(X + 7, op + 2 * AGSRC, otag); pair_poll(X + 14, op + 4 * AGSRC, otag);
              spin_guard(n);
            }
            pair_load(X + 21, after(op, X[7].x, otag) + 6 * AGSRC);
          }
          if (m == 3) pair_wait(X + 21, op + 6 * AGSRC, otag);
          ring.acquire(14 + m);
          const uint32_t b = ring.desc(14 + m);
          wg_fence();
#pragma unroll
          for (int t = 0; t < 7; t++) wgmma_rs_n56<H128>(res, X[7 * m + t].x, X[7 * m + t].y, X[7 * m + t].z, X[7 * m + t].w, b + t * 128);
          wg_commit();
          if (m) { wg_wait<1>(); ring.release(13 + m); }
        }
        wg_wait<0>();
        pin(res);
        pack28(res, rp);
        publish_stats(ag_stats(layer ^ 1) + j * AGSRC, res, xtag, lane);
        publish(ag_ptr(layer ^ 1) + j * AGSRC, rp, j & 1, xtag);
        ring.release(17);
      }
      uint32_t hf[56];
#pragma nv_diag_suppress 549
      const char* hb = (const char*)g_h + (uint32_t)((r * 64 + opaque(warp)) * 7168 + lane * 16);
      auto share_h = [&](int k) { stg4(hb + j * HSRC + k * 512, settag(hf[4 * k], tag), hf[4 * k + 1], hf[4 * k + 2], hf[4 * k + 3]); };
      const uint32_t park = base + SM_KVB + warp * 1792;
      uint4 Z[14];
      auto z_load = [&](int k0, int k1) {
        const char* p = hb + (j ^ 1) * HSRC;
        if (k0) p = after(p, Z[0].x, tag);
#pragma unroll
        for (int k = k0; k < k1; k++) Z[k] = ldg4(p + k * 512);
      };
      {
        float acc1[64];
        Act act;
        {
          const Ptr xp = ag_ptr(layer ^ 1);
          uint4 X[28];
          Norm nrm;
          {
            uint2 S[8];
            gather<2, true>(X, S, xp, ag_stats(layer ^ 1), xtag);
            nrm = combine_stats(S, lane);
          }
          act = make_act(nrm.f0, nrm.f1);
#pragma unroll
          for (int s = 0; s < 28; s++) {
            if (s % 7 == 0 && s) {
              pair_wait(X + s, xp + (s / 7) * 2 * AGSRC, xtag);
              if (s < 21) pair_load(X + s + 7, after(xp, X[s].x, xtag) + (s / 7 + 1) * 2 * AGSRC);
            }
            norm_step(X[s], nrm, ax, s);
            if ((s & 3) == 0) ring.acquire(18 + (s >> 2));
            wg_fence();
            if (s == 0) wgmma_rs_n128_z<H64>(acc1, X[s].x, X[s].y, X[s].z, X[s].w, ring.desc(18, 4096));
            else wgmma_rs_n128<H64>(acc1, X[s].x, X[s].y, X[s].z, X[s].w, ring.desc(18 + (s >> 2), 4096) + (s & 3) * 64);
            wg_commit();
            if ((s & 3) == 0 && s) { wg_wait<1>(); ring.release(17 + (s >> 2)); }
          }
#pragma unroll
          for (int k = 0; k < 3; k++) asm volatile("st.shared.v4.u32 [%0], {%1,%2,%3,%4};" ::"r"(park + lane * 16 + k * 512), "r"(rp[4 * k]), "r"(rp[4 * k + 1]), "r"(rp[4 * k + 2]), "r"(rp[4 * k + 3]) : "memory");
          asm volatile("st.shared.v2.u32 [%0], {%1,%2};" ::"r"(park + 1536 + lane * 8), "r"(rp[12]), "r"(rp[13]) : "memory");
          fence_async_smem();
          bar_wg(wg);
        }
        float acc2[96];
#pragma unroll
        for (int st = 0; st < 8; st++) {
          ring.acquire(25 + st);
          wg_fence();
          if (st == 0) wgmma_ss_n192_z<H64>(acc2, a0, ring.desc(25, 2048));
          else wgmma_ss_n192<H64>(acc2, a0 + (st >> 1) * 1024 + (st & 1) * 4, ring.desc(25 + st, 2048));
          wgmma_ss_n192<H64>(acc2, a0 + (st >> 1) * 1024 + (st & 1) * 4 + 2, ring.desc(25 + st, 2048) + 64);
          wg_commit();
          if (st == 0) { wg_wait<1>(); pin(acc1); ring.release(24); }
          else {
            if (st & 1) { geglu<64>(acc1, hf, act, (st >> 1) * 8); share_h(st >> 1); }
            wg_wait<1>(); ring.release(24 + st);
          }
        }
        {
          uint32_t prev = 32 % NSLOT, sl = 33 % NSLOT, ph = ((33 / NSLOT) & 1) ^ layer;
#pragma unroll 1
          for (int st = 8; st < 14; st++) {
            mbar_wait_c(base + BAR_FULL + 8 * sl, ph);
            const uint32_t a = a0 + (st >> 1) * 1024 + (st & 1) * 4, b = ring.desc(0, 2048) + sl * (SLOT_BYTES >> 4);
            wg_fence();
            wgmma_ss_n192<H64>(acc2, a, b);
            wgmma_ss_n192<H64>(acc2, a + 2, b + 64);
            wg_commit();
            wg_wait<1>();
            ring.release_slot(prev);
            prev = sl;
            if (++sl == NSLOT) { sl = 0; ph ^= 1; }
          }
        }
        float acc3[64];
#pragma unroll
        for (int st = 0; st < 7; st++) {
          ring.acquire(39 + st);
          wg_fence();
#pragma unroll
          for (int k = 0; k < 4; k++) {
            if (st + k == 0) wgmma_ss_n128_z<H64>(acc3, a0, ring.desc(39, 4096));
            else wgmma_ss_n128<H64>(acc3, a0 + st * 1024 + k * 2, ring.desc(39 + st, 4096) + k * 64);
          }
          wg_commit();
          if (st == 0) { wg_wait<1>(); pin(acc2); ring.release(38); }
          if (st < 6) { geglu<96>(acc2, hf + 16, act, st * 8); share_h(4 + st); }
          if (st) { wg_wait<1>(); ring.release(38 + st); }
        }
        wg_wait<0>();
        ring.release(45);
        ring.release_slot(AFREE);
        pin(acc3);
        z_load(0, 7);
#pragma unroll
        for (int k = 0; k < 4; k++) {
          geglu<64>(acc3, hf + 40, act, k * 8);
          share_h(10 + k);
        }
      }
      {
        float acc0[28], acc1[28];
        const char* pb = (const char*)g_part + (uint32_t)((r * 192 + opaque(warp)) * 1792);
        const Ptr pp{pb + lane * 16, pb + 1536 + lane * 8};
        auto z_wait = [&](int k0, int k1) {
          int n = 0;
          while (true) {
            uint32_t bad = 0;
#pragma unroll
            for (int k = k0; k < k1; k++) bad = or_xor(bad, Z[k].x, tag);
            if (!__any_sync(~0u, bad & 1u)) break;
#pragma unroll
            for (int k = k0; k < k1; k++) poll4(Z[k], hb + (j ^ 1) * HSRC + k * 512, tag);
            spin_guard(n);
          }
        };
        auto stage = [&](float (&acc)[28], int t) {
          const int p = dn_part(t);
          uint32_t b;
          if (t >= 6 && t < 14) { mbar_wait_c(base + BAR_W + 8 * (t - 6), layer); b = dlo(SM_A) + (t - 6) * 896; }
          else { ring.acquire(46 + (t & 7)); b = ring.desc(46 + (t & 7)); }
          wg_fence();
#pragma unroll
          for (int k = 0; k < 7; k++) {
            const int s = (p & 1) * 7 + k;
            const uint4 a = p < 2 ? make_uint4(hf[4 * s], hf[4 * s + 1], hf[4 * s + 2], hf[4 * s + 3]) : Z[s];
            if (p + k == 0) wgmma_rs_n56_z<H128>(acc, a.x, a.y, a.z, a.w, b);
            else wgmma_rs_n56<H128>(acc, a.x, a.y, a.z, a.w, b + k * 128);
          }
          wg_commit();
          if (t) wg_wait<1>();
          if (t >= 1 && t <= 6) ring.release(45 + t);
        };
        auto ship = [&](float (&acc)[28], int c) {
          pin(acc);
          uint32_t d[14];
          pack28(acc, d);
          send(pp + (((j + 2 + 2 * c) & 7) * 3 + c) * PSRC, d, tag);
        };
        struct In { uint4 R[3]; uint2 T; };
        In in[3];
        auto request = [&](int u) { const Ptr p = pp + (j * 3 + u) * PSRC; in[u].R[0] = ldg4(p.p16); in[u].R[1] = ldg4(p.p16 + 512); in[u].R[2] = ldg4(p.p16 + 1024); in[u].T = ldg2(p.p8); };
        pin(hf);
        stage(acc1, 0); stage(acc1, 1); stage(acc0, 2); stage(acc0, 3);
        z_wait(0, 7);
        z_load(7, 14);
        stage(acc1, 4); stage(acc0, 5);
        z_wait(7, 14);
        stage(acc1, 6);
        stage(acc0, 7);
        ship(acc1, 0);
        stage(acc1, 8);
        ship(acc0, 1);
        stage(acc1, 9); stage(acc1, 10);
        stage(acc1, 11);
        request(0);
        stage(acc0, 12);
        ship(acc1, 2);
        request(1);
        stage(acc0, 13);
        stage(acc0, 14);
        if (!layer) { if (wg) asm volatile("bar.arrive 5, 256;" ::: "memory"); else asm volatile("bar.arrive 4, 256;" ::: "memory"); }
        stage(acc0, 15);
        request(2);
#pragma unroll
        for (int k = 0; k < 3; k++) asm volatile("ld.shared.v4.u32 {%0,%1,%2,%3}, [%4];" : "=r"(rp[4 * k]), "=r"(rp[4 * k + 1]), "=r"(rp[4 * k + 2]), "=r"(rp[4 * k + 3]) : "r"(park + lane * 16 + k * 512) : "memory");
        asm volatile("ld.shared.v2.u32 {%0,%1}, [%2];" : "=r"(rp[12]), "=r"(rp[13]) : "r"(park + 1536 + lane * 8) : "memory");
        wg_wait<0>();
        pin(acc0);
#pragma unroll
        for (int i = 0; i < 14; i++) { res[2 * i] = acc0[2 * i] + bf_lo(rp[i]); res[2 * i + 1] = acc0[2 * i + 1] + bf_hi(rp[i]); }
        auto wait_in = [&](int u) {
          In& x = in[u];
          int n = 0;
          while (__any_sync(~0u, or_xor(or_xor(or_xor(x.T.x ^ tag, x.R[0].x, tag), x.R[1].x, tag), x.R[2].x, tag) & 1u)) { request(u); spin_guard(n); }
        };
        auto add2 = [](uint32_t a, uint32_t b) { uint32_t y; asm("add.rn.bf16x2 %0, %1, %2;" : "=r"(y) : "r"(a), "r"(b)); return y; };
        wait_in(0); wait_in(1); wait_in(2);
#pragma unroll
        for (int k = 0; k < 3; k++) {
          const uint4 a = in[0].R[k], b = in[1].R[k], c = in[2].R[k];
          const uint32_t x = add2(add2(a.x, b.x), c.x), y = add2(add2(a.y, b.y), c.y), z = add2(add2(a.z, b.z), c.z), w = add2(add2(a.w, b.w), c.w);
          res[8 * k] += bf_lo(x); res[8 * k + 1] += bf_hi(x); res[8 * k + 2] += bf_lo(y); res[8 * k + 3] += bf_hi(y);
          res[8 * k + 4] += bf_lo(z); res[8 * k + 5] += bf_hi(z); res[8 * k + 6] += bf_lo(w); res[8 * k + 7] += bf_hi(w);
        }
        const uint32_t x = add2(add2(in[0].T.x, in[1].T.x), in[2].T.x), y = add2(add2(in[0].T.y, in[1].T.y), in[2].T.y);
        res[24] += bf_lo(x); res[25] += bf_hi(x); res[26] += bf_lo(y); res[27] += bf_hi(y);
      }
      uint32_t d[14];
      pack28(res, d);
      const uint32_t par = parity();
      if (!layer) {
        publish_stats(ag_stats(0) + j * AGSRC, res, par, lane);
        publish(ag_ptr(0) + j * AGSRC, d, j & 1, par);
      } else {
        const uint32_t sb = base + SM_KVB + warp * 1792, sr = sb + (((lane >> 3) & 1) * 8 + (lane & 7)) * 112 + (lane >> 4) * 16;
#pragma unroll
        for (int i = 0; i < 3; i++) stsm4(sr + i * 32, d[4 * i], d[4 * i + 1], d[4 * i + 2], d[4 * i + 3]);
        asm volatile("stmatrix.sync.aligned.m8n8.x2.shared.b16 [%0], {%1,%2};" ::"r"(sr - (lane >> 4) * 16 + 96), "r"(d[12]), "r"(d[13]) : "memory");
        __syncwarp();
        const int ln = opaque(lane);
        char* o0 = (char*)(out + (uint32_t)((r * 128 + opaque(warp) * 16) * kD + 56 * j));
#pragma unroll
        for (int i = 0; i < 4; i++) {
          const int c = i * 32 + ln, row = c / 7;
          if (c < 112) {
            uint4 v;
            asm volatile("ld.shared.v4.u32 {%0,%1,%2,%3}, [%4];" : "=r"(v.x), "=r"(v.y), "=r"(v.z), "=r"(v.w) : "r"(sb + c * 16) : "memory");
            *(uint4*)(o0 + row * (kD * 2 - 112) + c * 16) = v;
          }
        }
        if (blockIdx.x == 0 && tid == 0) *(volatile uint32_t*)&g_parity = par ^ 1;
      }
    }
    asm volatile("barrier.cluster.arrive.relaxed.aligned;\nbarrier.cluster.wait.aligned;" ::: "memory");
  }
}

typedef CUresult (*EncodeFn)(CUtensorMap*, CUtensorMapDataType, cuuint32_t, void*, const cuuint64_t*, const cuuint64_t*, const cuuint32_t*,
                             const cuuint32_t*, CUtensorMapInterleave, CUtensorMapSwizzle, CUtensorMapL2promotion, CUtensorMapFloatOOBfill);

void map2(EncodeFn enc, CUtensorMap* m, const void* p, int cols, int rows, int bc, int br) {
  cuuint64_t d[2] = {(cuuint64_t)cols, (cuuint64_t)rows}, s[1] = {(cuuint64_t)cols * 2};
  cuuint32_t b[2] = {(cuuint32_t)bc, (cuuint32_t)br}, e[2] = {1, 1};
  enc(m, CU_TENSOR_MAP_DATA_TYPE_BFLOAT16, 2, (void*)p, d, s, b, e, CU_TENSOR_MAP_INTERLEAVE_NONE, CU_TENSOR_MAP_SWIZZLE_128B,
      CU_TENSOR_MAP_L2_PROMOTION_L2_128B, CU_TENSOR_MAP_FLOAT_OOB_FILL_NONE);
}
void map3(EncodeFn enc, CUtensorMap* m, const void* p, int groups, int rows) {
  cuuint64_t d[3] = {(cuuint64_t)kDF, (cuuint64_t)kD, (cuuint64_t)groups}, s[2] = {(cuuint64_t)kDF * 2, 64};
  cuuint32_t b[3] = {32, (cuuint32_t)rows, (cuuint32_t)groups}, e[3] = {1, 1, 1};
  enc(m, CU_TENSOR_MAP_DATA_TYPE_BFLOAT16, 3, (void*)p, d, s, b, e, CU_TENSOR_MAP_INTERLEAVE_NONE, CU_TENSOR_MAP_SWIZZLE_64B,
      CU_TENSOR_MAP_L2_PROMOTION_L2_128B, CU_TENSOR_MAP_FLOAT_OOB_FILL_NONE);
}

}

extern "C" void kernel_launch(void* const* d_in, const int* in_sizes, int n_in, void* d_out, int out_size) {
  (void)in_sizes; (void)n_in; (void)out_size;
  static EncodeFn enc = nullptr;
  if (!enc) {
    cudaDriverEntryPointQueryResult qr;
    cudaGetDriverEntryPoint("cuTensorMapEncodeTiled", (void**)&enc, cudaEnableDefault, &qr);
    cudaFuncSetAttribute(fused_kernel, cudaFuncAttributeMaxDynamicSharedMemorySize, SMEM_BYTES);
  }
  const void *x = d_in[0], *wqkv = d_in[1], *wphi = d_in[2], *wo = d_in[3], *wg = d_in[5], *wu = d_in[6], *wd = d_in[7];
  Maps m;
  for (int nb = 1; nb <= 1; nb++) {
    cuuint64_t d[3] = {(cuuint64_t)kD, (cuuint64_t)kS, 2}, s[2] = {(cuuint64_t)kD * 2, 128};
    cuuint32_t b[3] = {64, 128, (cuuint32_t)nb}, e[3] = {1, 1, 1};
    enc(&m.x, CU_TENSOR_MAP_DATA_TYPE_BFLOAT16, 3, (void*)x, d, s, b, e, CU_TENSOR_MAP_INTERLEAVE_NONE, CU_TENSOR_MAP_SWIZZLE_128B,
        CU_TENSOR_MAP_L2_PROMOTION_L2_128B, CU_TENSOR_MAP_FLOAT_OOB_FILL_NONE);
  }
  map2(enc, &m.kv, wqkv, 3 * kD, kD, 56, 64);
  map2(enc, &m.q, wqkv, 3 * kD, kD, 56, 56);
  map2(enc, &m.wo, wo, kD, kD, 56, 56);
  map2(enc, &m.dn, wd, kD, kDF, 56, 56);
  map3(enc, &m.g2, wg, 2, 64); map3(enc, &m.g3, wg, 3, 32);
  map3(enc, &m.u2, wu, 2, 64); map3(enc, &m.u3, wu, 3, 32);
  cudaLaunchConfig_t cfg = {};
  cfg.gridDim = dim3(128); cfg.blockDim = dim3(384); cfg.dynamicSmemBytes = SMEM_BYTES; cfg.stream = cudaStreamPerThread;
  cudaLaunchAttribute at[1];
  at[0].id = cudaLaunchAttributeClusterDimension; at[0].val.clusterDim.x = 2; at[0].val.clusterDim.y = 1; at[0].val.clusterDim.z = 1;
  cfg.attrs = at; cfg.numAttrs = 1;
  cudaLaunchKernelEx(&cfg, fused_kernel, m, (const __nv_bfloat16*)wqkv, (const __nv_bfloat16*)wphi, (const __nv_bfloat16*)wo, (const __nv_bfloat16*)wg,
                     (const __nv_bfloat16*)wu, (const __nv_bfloat16*)wd, (__nv_bfloat16*)d_out, 0);
}
```
